```python
import torch

def _softmax(x, axis=-1):
    return torch.softmax(x, dim=axis)
def _gelu(x):
    return torch.nn.functional.gelu(x, approximate="tanh")
def _silu(x):
    return torch.nn.functional.silu(x)
def _sigmoid(x):
    return torch.sigmoid(x)
def _layernorm(x, axis=-1, eps=1e-5):
    m = x.mean(dim=axis, keepdim=True)
    v = x.var(dim=axis, keepdim=True, unbiased=False)
    return (x - m) / torch.sqrt(v + eps)
def _scatter_add(tgt, idx, src, axis=0):
    return tgt.clone().index_add_(axis, idx, src)
def _segment_sum(src, seg, n):
    out = torch.zeros((n,) + src.shape[1:], dtype=src.dtype)
    return out.index_add_(0, seg, src)
def _pad(x, pw):
    flat = tuple(v for pair in reversed(pw) for v in pair)
    return torch.nn.functional.pad(x, flat)

kernel_name = 'interleave_layers__spectral_fnet__swiglu_ffn__prompt'

def setup_inputs():

    _w = (lambda a: (lambda t: t.to(torch.bfloat16) if t.is_floating_point() else t)(torch.as_tensor(a)))
    def _A_setup():
        B, S, D = 1, 2048, 640
        ns = torch.arange(S)[:, None] * torch.arange(S)[None, :]
        nd = torch.arange(D)[:, None] * torch.arange(D)[None, :]
        Ws_re = torch.cos(-2.0 * torch.pi * ns / S).to(float)
        Ws_im = torch.sin(-2.0 * torch.pi * ns / S).to(float)
        Wd_re = torch.cos(-2.0 * torch.pi * nd / D).to(float)
        Wd_im = torch.sin(-2.0 * torch.pi * nd / D).to(float)
        return {
            "x": _w((lambda *s: torch.randn(*s, dtype=torch.bfloat16) * 0.05)(B, S, D)),
            "dft_seq_re": _w(Ws_re),
            "dft_seq_im": _w(Ws_im),
            "dft_hid_re": _w(Wd_re),
            "dft_hid_im": _w(Wd_im),
        }
    _A_in = _A_setup()

    def _B_setup():
        B, S, D, F = 1, 2048, 640, 1728
        return {
            "x": _w((lambda *s: torch.randn(*s, dtype=torch.bfloat16) * 0.05)(B, S, D)),
            "w_gate": _w((lambda *s: torch.randn(*s, dtype=torch.bfloat16) * 0.4)(D, F)),
            "w_up": _w((lambda *s: torch.randn(*s, dtype=torch.bfloat16) * 0.4)(D, F)),
            "w_down": _w((lambda *s: torch.randn(*s, dtype=torch.bfloat16) * 0.4)(F, D)),
        }
    _B_in = _B_setup()

    return {
        "A_x": _A_in["x"],
        "A_dft_seq_re": _A_in["dft_seq_re"],
        "A_dft_seq_im": _A_in["dft_seq_im"],
        "A_dft_hid_re": _A_in["dft_hid_re"],
        "A_dft_hid_im": _A_in["dft_hid_im"],
        "B_x": _B_in["x"],
        "B_w_gate": _B_in["w_gate"],
        "B_w_up": _B_in["w_up"],
        "B_w_down": _B_in["w_down"],
    }

def reference(A_x, A_dft_seq_re, A_dft_seq_im, A_dft_hid_re, A_dft_hid_im, B_x, B_w_gate, B_w_up, B_w_down):
    def _A_ref(x, dft_seq_re, dft_seq_im, dft_hid_re, dft_hid_im):
        a = torch.einsum("bsd,ed->bse", x, dft_hid_re)
        b = torch.einsum("bsd,ed->bse", x, dft_hid_im)
        y = torch.einsum("ts,bse->bte", dft_seq_re, a) - torch.einsum("ts,bse->bte", dft_seq_im, b)
        return y

    def _B_ref(x, w_gate, w_up, w_down):
        g = _silu(x @ w_gate)
        u = x @ w_up
        return (g * u) @ w_down

    x = A_x
    x = x + _A_ref(_layernorm(x, axis=-1), A_dft_seq_re, A_dft_seq_im, A_dft_hid_re, A_dft_hid_im)
    x = x + _B_ref(_layernorm(x, axis=-1), B_w_gate, B_w_up, B_w_down)
    x = x + _A_ref(_layernorm(x, axis=-1), A_dft_seq_re, A_dft_seq_im, A_dft_hid_re, A_dft_hid_im)
    x = x + _B_ref(_layernorm(x, axis=-1), B_w_gate, B_w_up, B_w_down)
    return x
```

```cpp
#include <cuda_runtime.h>
#include <cuda_bf16.h>
#include <cuda.h>
#include <stdint.h>

namespace {

constexpr int SEQ = 2048, SEQP = 2080, DM = 640, FF = 1728;
constexpr int NCTA = 132, NWORK = 130;
constexpr int NTHREADS = 480;
constexpr int SKEW = 4;
constexpr int NSLOT = 5;
constexpr int SLOT_A = 16384, SLOT_B = 20480, SLOT = SLOT_A + SLOT_B;
constexpr int OFF_STG = NSLOT * SLOT;
constexpr int OFF_BAR = OFF_STG + 40960;
constexpr int OFF_TOKA = OFF_BAR + 384;
constexpr int OFF_TOKB = OFF_TOKA + 1280;
constexpr int OFF_FEAT = OFF_TOKB + 1920;
constexpr int OFF_SST = OFF_FEAT + 2048;
constexpr int OFF_EPOCH = OFF_SST + 1280;
constexpr int SMEM_BYTES = OFF_EPOCH + 32;
constexpr int B_FULL = 0, B_EMPTY = NSLOT, B_LEAD = 2 * NSLOT, B_PREP = 3 * NSLOT, B_STG = B_PREP + 1, B_EPOCH = B_STG + 2,
              B_LN = B_EPOCH + 1, B_XFREE = B_LN + 1, B_XFULL = B_XFREE + 1, B_SST = B_XFULL + 2, B_PRO = B_SST + 1, B_PAIR = B_PRO + 1,
              B_DEP = B_PAIR;
constexpr int OFF_DEP = 8;

constexpr int NR = 6, NRT = 2 * NR;
constexpr int NREP = 8;
constexpr int C_PRO = 0, C_PRO2 = NREP;
constexpr int C_AB = 2 * NREP;
constexpr int C_X1 = C_AB + 20;
constexpr int C_H = C_X1 + 52;
constexpr int C_X2 = C_H + 78;
constexpr int C_ST = C_X2 + 26;
constexpr int C_HS = C_ST + 52;
constexpr int C_XR = C_HS + 10;
constexpr int C_TOTAL = C_XR + 52;
constexpr int CSTRIDE = 32;


__device__ __align__(1024) __nv_bfloat16 g_abT[2 * SEQ * 1280];
__device__ __align__(1024) __nv_bfloat16 g_xA[SEQ * DM];
__device__ __align__(1024) __nv_bfloat16 g_xB[SEQ * DM];
__device__ __align__(1024) __nv_bfloat16 g_h[SEQ * FF];
__device__ __align__(1024) float2 g_stats[4][10][SEQP];
__device__ __align__(1024) float g_hs[10][13][32];
__device__ __align__(1024) float g_cs[2][2][FF];
__device__ __align__(1024) uint32_t g_cnt[C_TOTAL * CSTRIDE];
__device__ uint32_t g_claim[2][66];
__device__ uint32_t g_epoch;

struct Params {
  CUtensorMap hr, hi, x0, xa, xb, out, ab_ld[2], ab_st[2], cr, ci, wg, wu, wd, h;
  const __nv_bfloat16 *px0, *phr, *phi, *pwg, *pwu, *pwd, *pcr, *pci;
};

template<int TA, int TB, int SA = 1>
__device__ __forceinline__ void wgmma_n80(float (&d)[40], uint64_t da, uint64_t db, int scale_d) {
  asm volatile("{\n.reg .pred p;\nsetp.ne.b32 p, %42, 0;\n"
    "wgmma.mma_async.sync.aligned.m64n80k16.f32.bf16.bf16 {%0, %1, %2, %3, %4, %5, %6, %7, %8, %9, %10, %11, %12, %13, %14, %15, %16, %17, %18, %19, %20, %21, %22, %23, %24, %25, %26, %27, %28, %29, %30, %31, %32, %33, %34, %35, %36, %37, %38, %39}, %40, %41, p, %45, 1, %43, %44;\n}\n"
    : "+f"(d[0]), "+f"(d[1]), "+f"(d[2]), "+f"(d[3]), "+f"(d[4]), "+f"(d[5]), "+f"(d[6]), "+f"(d[7]), "+f"(d[8]), "+f"(d[9]), "+f"(d[10]), "+f"(d[11]), "+f"(d[12]), "+f"(d[13]), "+f"(d[14]), "+f"(d[15]), "+f"(d[16]), "+f"(d[17]), "+f"(d[18]), "+f"(d[19]), "+f"(d[20]), "+f"(d[21]), "+f"(d[22]), "+f"(d[23]), "+f"(d[24]), "+f"(d[25]), "+f"(d[26]), "+f"(d[27]), "+f"(d[28]), "+f"(d[29]), "+f"(d[30]), "+f"(d[31]), "+f"(d[32]), "+f"(d[33]), "+f"(d[34]), "+f"(d[35]), "+f"(d[36]), "+f"(d[37]), "+f"(d[38]), "+f"(d[39])
    : "l"(da), "l"(db), "r"(scale_d), "n"(TA), "n"(TB), "n"(SA));
}
template<int TA, int TB, int SA = 1>
__device__ __forceinline__ void wgmma_n160(float (&d)[80], uint64_t da, uint64_t db, int scale_d) {
  asm volatile("{\n.reg .pred p;\nsetp.ne.b32 p, %82, 0;\n"
    "wgmma.mma_async.sync.aligned.m64n160k16.f32.bf16.bf16 {%0, %1, %2, %3, %4, %5, %6, %7, %8, %9, %10, %11, %12, %13, %14, %15, %16, %17, %18, %19, %20, %21, %22, %23, %24, %25, %26, %27, %28, %29, %30, %31, %32, %33, %34, %35, %36, %37, %38, %39, %40, %41, %42, %43, %44, %45, %46, %47, %48, %49, %50, %51, %52, %53, %54, %55, %56, %57, %58, %59, %60, %61, %62, %63, %64, %65, %66, %67, %68, %69, %70, %71, %72, %73, %74, %75, %76, %77, %78, %79}, %80, %81, p, %85, 1, %83, %84;\n}\n"
    : "+f"(d[0]), "+f"(d[1]), "+f"(d[2]), "+f"(d[3]), "+f"(d[4]), "+f"(d[5]), "+f"(d[6]), "+f"(d[7]), "+f"(d[8]), "+f"(d[9]), "+f"(d[10]), "+f"(d[11]), "+f"(d[12]), "+f"(d[13]), "+f"(d[14]), "+f"(d[15]), "+f"(d[16]), "+f"(d[17]), "+f"(d[18]), "+f"(d[19]), "+f"(d[20]), "+f"(d[21]), "+f"(d[22]), "+f"(d[23]), "+f"(d[24]), "+f"(d[25]), "+f"(d[26]), "+f"(d[27]), "+f"(d[28]), "+f"(d[29]), "+f"(d[30]), "+f"(d[31]), "+f"(d[32]), "+f"(d[33]), "+f"(d[34]), "+f"(d[35]), "+f"(d[36]), "+f"(d[37]), "+f"(d[38]), "+f"(d[39]), "+f"(d[40]), "+f"(d[41]), "+f"(d[42]), "+f"(d[43]), "+f"(d[44]), "+f"(d[45]), "+f"(d[46]), "+f"(d[47]), "+f"(d[48]), "+f"(d[49]), "+f"(d[50]), "+f"(d[51]), "+f"(d[52]), "+f"(d[53]), "+f"(d[54]), "+f"(d[55]), "+f"(d[56]), "+f"(d[57]), "+f"(d[58]), "+f"(d[59]), "+f"(d[60]), "+f"(d[61]), "+f"(d[62]), "+f"(d[63]), "+f"(d[64]), "+f"(d[65]), "+f"(d[66]), "+f"(d[67]), "+f"(d[68]), "+f"(d[69]), "+f"(d[70]), "+f"(d[71]), "+f"(d[72]), "+f"(d[73]), "+f"(d[74]), "+f"(d[75]), "+f"(d[76]), "+f"(d[77]), "+f"(d[78]), "+f"(d[79])
    : "l"(da), "l"(db), "r"(scale_d), "n"(TA), "n"(TB), "n"(SA));
}
template<int N, int TA, int TB, int SA = 1> __device__ __forceinline__ void wgmma(float (&d)[N/2], uint64_t da, uint64_t db, int scale_d) {
  if constexpr (N == 80) wgmma_n80<TA,TB,SA>(d, da, db, scale_d);
  else if constexpr (N == 160) wgmma_n160<TA,TB,SA>(d, da, db, scale_d);
}


__device__ __forceinline__ uint32_t smem_u32(const void* p) { return (uint32_t)__cvta_generic_to_shared(p); }
__device__ __forceinline__ void mbar_init(uint32_t bar, int cnt) { asm volatile("mbarrier.init.shared::cta.b64 [%0], %1;" ::"r"(bar), "r"(cnt)); }
__device__ __forceinline__ void mbar_expect_tx(uint32_t bar, uint32_t bytes) { asm volatile("mbarrier.arrive.expect_tx.shared::cta.b64 _, [%0], %1;" ::"r"(bar), "r"(bytes) : "memory"); }
__device__ __forceinline__ void mbar_arrive(uint32_t bar) { asm volatile("mbarrier.arrive.shared::cta.b64 _, [%0];" ::"r"(bar) : "memory"); }
__device__ __forceinline__ void mbar_wait(uint32_t bar, uint32_t parity) {
  asm volatile("{\n.reg .pred p;\n.reg .u32 it;\nmov.u32 it, 0;\n"
               "LW:\nmbarrier.try_wait.parity.shared::cta.b64 p, [%0], %1;\n@p bra LD;\n"
               "add.u32 it, it, 1;\nsetp.lt.u32 p, it, 0x4000000;\n@p bra LW;\ntrap;\nLD:\n}"
               ::"r"(bar), "r"(parity) : "memory");
}
__device__ __forceinline__ void mbar_wait_cluster(uint32_t bar, uint32_t parity) {
  asm volatile("{\n.reg .pred p;\n.reg .u32 it;\nmov.u32 it, 0;\n"
               "LW:\nmbarrier.try_wait.parity.acquire.cluster.shared::cta.b64 p, [%0], %1;\n@p bra LD;\n"
               "add.u32 it, it, 1;\nsetp.lt.u32 p, it, 0x4000000;\n@p bra LW;\ntrap;\nLD:\n}"
               ::"r"(bar), "r"(parity) : "memory");
}
__device__ __forceinline__ void tma_load(uint32_t dst, const CUtensorMap* m, int c0, int c1, uint32_t bar) {
  asm volatile("cp.async.bulk.tensor.2d.shared::cluster.global.mbarrier::complete_tx::bytes [%0], [%1, {%3, %4}], [%2];"
               ::"r"(dst), "l"((uint64_t)m), "r"(bar), "r"(c0), "r"(c1) : "memory");
}
__device__ __forceinline__ void tma_store(const CUtensorMap* m, int c0, int c1, uint32_t src) {
  asm volatile("cp.async.bulk.tensor.2d.global.shared::cta.bulk_group [%0, {%2, %3}], [%1];"
               ::"l"((uint64_t)m), "r"(src), "r"(c0), "r"(c1) : "memory");
}
__device__ __forceinline__ void bulk_store(void* dst, uint32_t src, uint32_t bytes) {
  asm volatile("cp.async.bulk.global.shared::cta.bulk_group [%0], [%1], %2;" ::"l"(dst), "r"(src), "r"(bytes) : "memory");
}
__device__ __forceinline__ void bulk_commit_wait_read() { asm volatile("cp.async.bulk.commit_group;\ncp.async.bulk.wait_group.read 0;" ::: "memory"); }
__device__ __forceinline__ void bulk_wait() { asm volatile("cp.async.bulk.wait_group 0;" ::: "memory"); }
__device__ __forceinline__ void fence_async() { asm volatile("fence.proxy.async.global;" ::: "memory"); }
__device__ __forceinline__ void fence_async_smem() { asm volatile("fence.proxy.async.shared::cta;" ::: "memory"); }
__device__ __forceinline__ void bar_sync(int id, int n) { asm volatile("bar.sync %0, %1;" ::"r"(id), "r"(n) : "memory"); }
__device__ __forceinline__ void cluster_sync() {
  asm volatile("barrier.cluster.arrive.release.aligned;\nbarrier.cluster.wait.acquire.aligned;" ::: "memory");
}
__device__ __forceinline__ void wg_fence() { asm volatile("wgmma.fence.sync.aligned;" ::: "memory"); }
__device__ __forceinline__ void wg_commit() { asm volatile("wgmma.commit_group.sync.aligned;" ::: "memory"); }
template <int N> __device__ __forceinline__ void wg_wait() { asm volatile("wgmma.wait_group.sync.aligned %0;" ::"n"(N) : "memory"); }
__device__ __forceinline__ uint64_t make_desc(uint32_t lo) {
  return (uint64_t)lo | ((uint64_t)(1024 >> 4) << 32) | ((uint64_t)1 << 62);
}
__device__ __forceinline__ int uni(int v) { return (int)__reduce_max_sync(0xffffffffu, (unsigned)v); }
__device__ __forceinline__ void signal(int idx) {
  asm volatile("red.release.gpu.global.add.u32 [%0], 1;" ::"l"(g_cnt + idx * CSTRIDE) : "memory");
}
__device__ __forceinline__ void signal_all(int idx) {
  signal(idx);
#pragma unroll
  for (int i = 1; i < NREP; i++) asm volatile("red.relaxed.gpu.global.add.u32 [%0], 1;" ::"l"(g_cnt + (idx + i) * CSTRIDE) : "memory");
}
__device__ __forceinline__ uint32_t ld_rlx(const uint32_t* p) {
  uint32_t v;
  asm volatile("ld.relaxed.gpu.global.u32 %0, [%1];" : "=r"(v) : "l"(p) : "memory");
  return v;
}
__device__ __forceinline__ float4 ld_l2(const float4* p) {
  float4 v;
  asm volatile("ld.relaxed.gpu.global.v4.f32 {%0,%1,%2,%3}, [%4];" : "=f"(v.x), "=f"(v.y), "=f"(v.z), "=f"(v.w) : "l"(p) : "memory");
  return v;
}
__device__ __forceinline__ uint32_t mapa(uint32_t a, uint32_t rank) {
  uint32_t r;
  asm("mapa.shared::cluster.u32 %0, %1, %2;" : "=r"(r) : "r"(a), "r"(rank));
  return r;
}
__device__ __forceinline__ uint32_t lds_vol(uint32_t a) {
  uint32_t v;
  asm volatile("ld.volatile.shared.u32 %0, [%1];" : "=r"(v) : "r"(a) : "memory");
  return v;
}
__device__ __forceinline__ void wait_cnt(int idx, uint32_t expected, uint32_t epoch, uint32_t s_urg, uint32_t urg) {
  const uint32_t* p = g_cnt + idx * CSTRIDE;
  const uint32_t target = (epoch + 1) * expected;
  uint32_t it = 0;
#pragma unroll 1
  while (true) {
    if ((int)(ld_rlx(p) - target) >= 0) return;
    if (lds_vol(s_urg) >= urg) break;
    __nanosleep(400);
    if (++it > 0x400000) __trap();
  }
  uint32_t v0 = ld_rlx(p); __nanosleep(200);
  uint32_t v1 = ld_rlx(p);
#pragma unroll 1
  while (true) {
    if ((int)(v0 - target) >= 0) return;
    v0 = ld_rlx(p);
    if ((int)(v1 - target) >= 0) return;
    v1 = ld_rlx(p);
    if (++it > 0x400000) __trap();
  }
}
__device__ __forceinline__ uint32_t pack_bf16(float lo, float hi) {
  uint32_t r;
  asm("cvt.rn.bf16x2.f32 %0, %1, %2;" : "=r"(r) : "f"(hi), "f"(lo));
  return r;
}
__device__ __forceinline__ float bf_lo(uint32_t v) { return __uint_as_float(v << 16); }
__device__ __forceinline__ float bf_hi(uint32_t v) { return __uint_as_float(v & 0xFFFF0000u); }
__device__ __forceinline__ void stsm4t(uint32_t a, uint32_t r0, uint32_t r1, uint32_t r2, uint32_t r3) {
  asm volatile("stmatrix.sync.aligned.m8n8.x4.trans.shared.b16 [%0], {%1,%2,%3,%4};" ::"r"(a), "r"(r0), "r"(r1), "r"(r2), "r"(r3));
}
__device__ __forceinline__ void ldsm4t(uint32_t a, uint32_t& r0, uint32_t& r1, uint32_t& r2, uint32_t& r3) {
  asm volatile("ldmatrix.sync.aligned.m8n8.x4.trans.shared.b16 {%0,%1,%2,%3}, [%4];" : "=r"(r0), "=r"(r1), "=r"(r2), "=r"(r3) : "r"(a) : "memory");
}
__device__ __forceinline__ uint4 lds128(uint32_t a) {
  uint4 v;
  asm volatile("ld.shared.v4.u32 {%0,%1,%2,%3}, [%4];" : "=r"(v.x), "=r"(v.y), "=r"(v.z), "=r"(v.w) : "r"(a) : "memory");
  return v;
}
__device__ __forceinline__ void sts128(uint32_t a, uint32_t x, uint32_t y, uint32_t z, uint32_t w) {
  asm volatile("st.shared.v4.u32 [%0], {%1,%2,%3,%4};" ::"r"(a), "r"(x), "r"(y), "r"(z), "r"(w) : "memory");
}
__device__ __forceinline__ float4 lds128f(uint32_t a) {
  float4 v;
  asm volatile("ld.shared.v4.f32 {%0,%1,%2,%3}, [%4];" : "=f"(v.x), "=f"(v.y), "=f"(v.z), "=f"(v.w) : "r"(a) : "memory");
  return v;
}
__device__ __forceinline__ float lds32f(uint32_t a) {
  float v;
  asm volatile("ld.shared.f32 %0, [%1];" : "=f"(v) : "r"(a) : "memory");
  return v;
}
__device__ __forceinline__ float2 lds64f(uint32_t a) {
  float2 v;
  asm volatile("ld.shared.v2.f32 {%0,%1}, [%2];" : "=f"(v.x), "=f"(v.y) : "r"(a) : "memory");
  return v;
}
__device__ __forceinline__ float ex2_fast(float x) { float y; asm("ex2.approx.ftz.f32 %0, %1;" : "=f"(y) : "f"(x)); return y; }
__device__ __forceinline__ float rcp_fast(float x) { float y; asm("rcp.approx.ftz.f32 %0, %1;" : "=f"(y) : "f"(x)); return y; }
__device__ __forceinline__ void sts64f(uint32_t a, float x, float y) {
  asm volatile("st.shared.v2.f32 [%0], {%1,%2};" ::"r"(a), "f"(x), "f"(y) : "memory");
}

__device__ __forceinline__ int round_ndep(int R) { const int r = R >= NR ? R - NR : R; return R == 0 ? 0 : (r == 1 ? 1 : (r < 3 ? 2 : (r == 5 ? 3 : 0))); }
__device__ __forceinline__ void k_segment(int R, int r, int kap, int m5, int kb0, int sg, int& first, int& stride, int& count) {
  stride = 1;
  if (r == 1) { first = sg == 0 ? kb0 : (sg == 1 ? 0 : kb0 + 2); count = sg == 0 ? 2 : (sg == 1 ? kb0 : (sg == 2 ? 30 - kb0 : 0)); }
  else if (r == 5) {
    first = sg == 0 ? (m5 < 3 ? 0 : 5) : (sg == 1 ? (kap ? 10 : 13) : 20 + 4 * kap);
    count = sg == 0 ? (kap ? 10 - first : 0) : (sg == 1 ? (kap ? 3 : 7) : (sg == 2 ? 4 - kap : 0));
  } else if (r == 4 && kap && m5 < 3) { first = 0; count = sg == 0 ? 5 : 0; }
  else if (r == 2 || R == NR) {
    stride = 2;
    first = sg == 0 ? 2 * m5 : (sg == 1 ? 0 : (sg == 2 ? 2 * m5 + 2 : 1));
    count = sg == 0 ? 1 : (sg == 1 ? m5 : (sg == 2 ? 4 - m5 : 5));
  } else { first = 0; count = sg == 0 ? 10 : 0; }
}
__device__ __forceinline__ void wait_dep(uint32_t bars, uint32_t s_urg, uint32_t n) {
  if (n == 0) return;
  asm volatile("red.shared.max.u32 [%0], %1;" ::"r"(s_urg), "r"(n) : "memory");
  mbar_wait(bars + 8 * (B_DEP + n), 0);
  fence_async();
}

__device__ __forceinline__ float sum8(const uint4& a) {
  return ((bf_lo(a.x) + bf_hi(a.x)) + (bf_lo(a.y) + bf_hi(a.y))) + ((bf_lo(a.z) + bf_hi(a.z)) + (bf_lo(a.w) + bf_hi(a.w)));
}
__device__ __forceinline__ float2 slice_stats(const uint4 (&v)[8]) {
  const float s = ((sum8(v[0]) + sum8(v[1])) + (sum8(v[2]) + sum8(v[3]))) + ((sum8(v[4]) + sum8(v[5])) + (sum8(v[6]) + sum8(v[7])));
  const float mean = s * (1.f / 64.f);
  float q0 = 0.f, q1 = 0.f, q2 = 0.f, q3 = 0.f;
#pragma unroll
  for (int c = 0; c < 8; c++) {
    float d;
    d = bf_lo(v[c].x) - mean; q0 += d * d; d = bf_hi(v[c].x) - mean; q1 += d * d;
    d = bf_lo(v[c].y) - mean; q2 += d * d; d = bf_hi(v[c].y) - mean; q3 += d * d;
    d = bf_lo(v[c].z) - mean; q0 += d * d; d = bf_hi(v[c].z) - mean; q1 += d * d;
    d = bf_lo(v[c].w) - mean; q2 += d * d; d = bf_hi(v[c].w) - mean; q3 += d * d;
  }
  return make_float2(mean, (q0 + q1) + (q2 + q3));
}

__device__ __forceinline__ void map_prefetch(const CUtensorMap* m) {
  asm volatile("prefetch.tensormap [%0];" ::"l"((uint64_t)m) : "memory");
}
__device__ __forceinline__ int tpc_order(int t) {
  int g, i;
  if (t < 32) { g = t & 7; i = t >> 3; }
  else if (t < 60) { const int d = (t - 32) / 7; g = t - 32 - d * 7 + 1; i = 4 + d; }
  else if (t < 62) { g = t - 54; i = 8; }
  else { g = 0; i = t - 58; }
  return (g == 0 ? 58 : (g - 1) * 8 + (g == 7)) + i;
}
__device__ __forceinline__ void bulk_load(uint32_t dst, const void* src, uint32_t bytes, uint32_t bar) {
  asm volatile("cp.async.bulk.shared::cluster.global.mbarrier::complete_tx::bytes [%0], [%1], %2, [%3];"
               ::"r"(dst), "l"(src), "r"(bytes), "r"(bar) : "memory");
}

struct Ring { uint32_t slot, phase; };
__device__ __forceinline__ void ring_next(Ring& r) { if (++r.slot == NSLOT) { r.slot = 0; r.phase ^= 1; } }

__device__ __forceinline__ void warp_arrive(uint32_t bar, int lane) {
  __syncwarp();
  if (lane == 0) mbar_arrive(bar);
}

template <int NI, int AMN>
__device__ __forceinline__ void mainloop(float (&acc)[NI][80 / NI], uint32_t sb, Ring& ring_io, int nkb, int wg, int lane, uint32_t lead_ph) {
  const uint32_t bars = sb + OFF_BAR;
  uint32_t prev = 0;
  Ring ring{(uint32_t)uni(ring_io.slot), (uint32_t)uni(ring_io.phase)};
  const uint32_t base = ((sb >> 4) | 0x10000u);
  const uint32_t aoff = NI == 2 ? 0 : wg * (8192 >> 4), boff = (SLOT_A >> 4) + (NI == 2 ? wg * (10240 >> 4) : 0);
#pragma unroll
  for (int j = 0; j < NI; j++)
#pragma unroll
    for (int i = 0; i < 80 / NI; i++) acc[j][i] = 0.f;
#pragma unroll 1
  for (int kb = 0; kb < nkb; kb++) {
    mbar_wait(bars + 8 * (B_FULL + ring.slot), ring.phase);
    if (wg && kb == nkb - SKEW) mbar_wait(bars + 8 * B_LEAD, lead_ph);
    const uint32_t la = base + ring.slot * (SLOT >> 4);
    wg_fence();
#pragma unroll
    for (int k = 0; k < 4; k++) {
      const uint32_t ak = AMN ? k * 128 : k * 2;
      const uint64_t db = make_desc(la + boff + k * 2);
#pragma unroll
      for (int j = 0; j < NI; j++) wgmma<160 / NI, AMN, 0>(acc[j], make_desc(la + aoff + j * (8192 >> 4) + ak), db, 1);
    }
    wg_commit();
    if (kb > 0) {
      wg_wait<1>();
      if (lane == 0) mbar_arrive(bars + 8 * (B_EMPTY + prev));
    }
    prev = ring.slot;
    ring_next(ring);
  }
  if (threadIdx.x == 0) mbar_arrive(bars + 8 * B_LEAD);
  wg_wait<0>();
  if (lane == 0) mbar_arrive(bars + 8 * (B_EMPTY + prev));
  ring_io = ring;
}

__device__ __noinline__ void claim_tpc(uint32_t smid, uint32_t peer, uint32_t rank, volatile uint32_t* out) {
  if (threadIdx.x == 0 && rank == 0) {
    const uint32_t tag = ld_rlx(&g_epoch) + 1;
    atomicExch(&g_claim[0][smid >> 1], tag); atomicExch(&g_claim[0][peer >> 1], tag);
    uint32_t t = smid >> 1, it = 0;
    while (!(ld_rlx(&g_claim[0][t]) == tag && atomicExch(&g_claim[1][t], tag) != tag)) {
      t = t == 65 ? 0 : t + 1;
      if (++it > (1u << 22)) __trap();
    }
    *out = t;
  }
  __syncwarp();
}

__global__ void __cluster_dims__(2, 1, 1) __launch_bounds__(NTHREADS, 1) fused_kernel(const __grid_constant__ Params P) {
  extern __shared__ __align__(1024) uint8_t smem_raw[];
  const uint32_t sb = smem_u32(smem_raw);
  const uint32_t bars = sb + OFF_BAR;
  const int warp = uni(threadIdx.x >> 5), lane = threadIdx.x & 31;
  uint32_t smid, nsm, rank;
  asm volatile("mov.u32 %0, %%smid;" : "=r"(smid));
  asm volatile("mov.u32 %0, %%nsmid;" : "=r"(nsm));
  asm volatile("mov.u32 %0, %%cluster_ctarank;" : "=r"(rank));

  const int pb = blockIdx.x, pt = pb / 13, pr0 = min((pb - pt * 13) * 10, 118);
  if (threadIdx.x == 384 && pb < NWORK) {
    mbar_init(bars + 8 * B_PRO, 1);
    asm volatile("fence.mbarrier_init.release.cluster;" ::: "memory");
    mbar_expect_tx(bars + 8 * B_PRO, 20480 + 12800);
    bulk_load(sb + OFF_STG, P.px0 + (size_t)min(pb, 127) * 16 * DM, 20480, bars + 8 * B_PRO);
    bulk_load(sb + OFF_STG + 20480, (pt < 5 ? P.phr + (size_t)(pt * 128 + pr0) * DM : P.phi + (size_t)((pt - 5) * 128 + pr0) * DM), 12800, bars + 8 * B_PRO);
  }
  if (threadIdx.x == 288) { map_prefetch(&P.x0); map_prefetch(&P.hr); map_prefetch(&P.hi); }
  if (threadIdx.x >= 320 && threadIdx.x < 333) map_prefetch(&P.xa + (threadIdx.x - 320));
  if (threadIdx.x <= B_DEP + 16 && threadIdx.x != B_PRO) {
    const int i = threadIdx.x;
    const int cnt = (i < B_EMPTY || i == B_PAIR) ? 2 : (i < B_LEAD || i == B_SST ? 8 : (i == B_STG || i == B_STG + 1 ? 4 : (i == B_LN ? 3 : 1)));
    mbar_init(bars + 8 * i, cnt);
    if (i == 0) {
      if (sb & 1023) __trap();
      *reinterpret_cast<volatile uint32_t*>(smem_raw + OFF_EPOCH + OFF_DEP + 4) = 0;
      *reinterpret_cast<volatile uint32_t*>(smem_raw + OFF_EPOCH + 24) = smid;
    }
    asm volatile("fence.mbarrier_init.release.cluster;" ::: "memory");
  }
  cluster_sync();
  int lid = blockIdx.x;
  if (nsm == NCTA) {
    uint32_t peer;
    asm volatile("ld.shared::cluster.u32 %0, [%1];" : "=r"(peer) : "r"(mapa(sb + OFF_EPOCH + 24, rank ^ 1)) : "memory");
    uint32_t tpc = smid >> 1;
    if (peer != (smid ^ 1)) {
      claim_tpc(smid, peer, rank, reinterpret_cast<volatile uint32_t*>(smem_raw + OFF_EPOCH + 28));
      cluster_sync();
      asm volatile("ld.shared::cluster.u32 %0, [%1];" : "=r"(tpc) : "r"(mapa(sb + OFF_EPOCH + 28, 0)) : "memory");
      cluster_sync();
    }
    lid = tpc_order(tpc) * 2 + rank;
  }
  lid = uni(lid);
  volatile uint32_t* s_epoch = reinterpret_cast<volatile uint32_t*>(smem_raw + OFF_EPOCH);
  const uint32_t s_dep = sb + OFF_EPOCH + OFF_DEP;
  const int pp = lid >> 1, T = pp < 39 ? pp / 3 : (pp - 39) >> 1, mem = (pp < 39 ? pp - T * 3 : 3 + ((pp - 39) & 1)) * 2 + (lid & 1);
  const int tok0 = T * 160, kap = mem & 1, m5 = mem >> 1;
  const int ft = kap * 5 + m5;
  const int kb0 = (5 * T + 1) >> 1;
  const int nrt = lid < NWORK ? NRT : 0;
  const bool helper = kap && m5 < 2;
  const int fc = 20 + (mem < 6 ? m5 : mem - 3);
  const uint32_t stg = sb + OFF_STG;

  if (warp >= 8 && warp < 12) {
    if (warp == 8) {
      if (lane == 0) {
        Ring ring{0, 1};
        uint32_t ndep = 0;
#pragma unroll 1
        for (int R = 0; R < nrt; R++) {
          const int layer = R >= NR, r = R - NR * layer;
          const int f = r == 4 ? fc : (r - 2) * 10 + mem;
          if (r == 4 && mem == 5) continue;
          const CUtensorMap *m0, *m1; int c0, c1;
          if (r == 0) { m0 = m1 = kap ? &P.hi : &P.hr; c0 = c1 = m5 * 128; }
          else if (r == 1) { m0 = m1 = &P.ab_ld[layer]; c0 = kap * 640 + m5 * 128; c1 = c0 + 64; }
          else if (r < 5 && !(r == 4 && helper)) { m0 = &P.wg; m1 = &P.wu; c0 = c1 = f * 64; }
          else { m0 = m1 = &P.wd; c0 = (r == 4 ? m5 + 3 : m5) * 128; c1 = c0 + 64; }
#pragma unroll 1
          for (int sg = 0; sg < 4; sg++) {
            int kc, st, cnt;
            k_segment(R, r, kap, m5, kb0, sg, kc, st, cnt);
            kc *= 64; st *= 64;
            if (r == 1 && sg == 0) { mbar_wait(bars + 8 * (B_DEP + 15 + layer), 0); fence_async(); }
            if (r == 1 && sg == 1) wait_dep(bars, s_dep + 4, ndep + 1);
            if (r == 0) {
#pragma unroll 1
              for (; cnt > 0; cnt--, kc += st) {
                mbar_wait(bars + 8 * (B_EMPTY + ring.slot), ring.phase);
                mbar_expect_tx(bars + 8 * (B_FULL + ring.slot), SLOT_A);
                tma_load(sb + ring.slot * SLOT, m0, kc, c0, bars + 8 * (B_FULL + ring.slot));
                ring_next(ring);
              }
            } else {
#pragma unroll 1
              for (; cnt > 0; cnt--, kc += st) {
                mbar_wait(bars + 8 * (B_EMPTY + ring.slot), ring.phase);
                mbar_expect_tx(bars + 8 * (B_FULL + ring.slot), SLOT_A);
                tma_load(sb + ring.slot * SLOT, m0, c0, kc, bars + 8 * (B_FULL + ring.slot));
                tma_load(sb + ring.slot * SLOT + 8192, m1, c1, kc, bars + 8 * (B_FULL + ring.slot));
                ring_next(ring);
              }
            }
          }
          ndep += round_ndep(R);
        }
      }
    } else if (warp == 9) {
      if (lane == 0) {
        Ring ring{0, 1};
        uint32_t ndep = 0, pairph = 0;
#pragma unroll 1
        for (int R = 0; R < nrt; R++) {
          const int layer = R >= NR, r = R - NR * layer;
          if (r == 4 && mem == 5) continue;
          const CUtensorMap* map = r == 0 ? (layer ? &P.xb : &P.x0) : (r == 1 ? (kap ? &P.ci : &P.cr) : (r < 5 && !(r == 4 && helper) ? &P.xa : &P.h));
          const int sw = (r == 1 || r == 5) ? kap : 0;
          const int t0 = tok0 + 80 * sw, t1 = tok0 + 80 * (sw ^ 1);
#pragma unroll 1
          for (int sg = 0; sg < 4; sg++) {
            int kc, st, cnt;
            k_segment(R, r, kap, m5, kb0, sg, kc, st, cnt);
            kc *= 64; st *= 64;
            if (r == 2 || R == NR) {
              if (sg == 0) {
                asm volatile("red.shared.max.u32 [%0], %1;" ::"r"(s_dep + 4), "r"(ndep + 1) : "memory");
                mbar_wait_cluster(bars + 8 * B_PAIR, pairph); pairph ^= 1;
                fence_async();
              }
              if (sg & 1) wait_dep(bars, s_dep + 4, ndep + 1 + (sg >> 1));
            }
            if ((r == 5 && sg < 3) || (r == 4 && helper && sg == 0)) wait_dep(bars, s_dep + 4, ndep + 1 + sg);
#pragma unroll 1
            for (; cnt > 0; cnt--, kc += st) {
              mbar_wait(bars + 8 * (B_EMPTY + ring.slot), ring.phase);
              mbar_expect_tx(bars + 8 * (B_FULL + ring.slot), SLOT_B);
              tma_load(sb + ring.slot * SLOT + SLOT_A, map, kc, t0, bars + 8 * (B_FULL + ring.slot));
              tma_load(sb + ring.slot * SLOT + SLOT_A + 10240, map, kc, t1, bars + 8 * (B_FULL + ring.slot));
              ring_next(ring);
            }
          }
          ndep += round_ndep(R);
        }
      }
    } else if (warp == 10) {
      if (lane == 0) {
        const uint32_t b_prep = bars + 8 * B_PREP, b_stg = bars + 8 * B_STG;
        uint32_t ph_stg = 0, ndep = 0;
#pragma unroll 1
        for (int R = 0; R < nrt; R++) {
          const int layer = R >= NR, r = R - NR * layer;
          const uint32_t ndep0 = ndep;
          ndep += round_ndep(R);
          if (r == 4 && mem == 5) continue;
          if (r == 1 || r == 5) {
            mbar_expect_tx(bars + 8 * B_XFULL, 10240);
            mbar_expect_tx(bars + 8 * (B_XFULL + 1), 10240);
            asm volatile("mbarrier.arrive.release.cluster.shared::cluster.b64 _, [%0];" ::"r"(mapa(bars + 8 * B_XFREE, rank ^ 1)) : "memory");
            const CUtensorMap* rm = r == 5 ? (m5 < 3 ? &P.xa : (layer ? &P.out : &P.xb)) : (layer ? &P.xb : &P.x0);
            wait_dep(bars, s_dep + 4, ndep0);
            if (r == 5 && m5 >= 3) { wait_cnt(C_XR + (layer * 13 + T) * 2 + m5 - 3, 1, *s_epoch, s_dep + 4, 0xffffffffu); fence_async(); }
            fence_async_smem();
            mbar_expect_tx(b_prep, 20480);
            tma_load(stg, rm, m5 * 128, tok0 + 80 * kap, b_prep);
            tma_load(stg + 10240, rm, m5 * 128 + 64, tok0 + 80 * kap, b_prep);
          } else if (r == 4 && helper) {
            wait_dep(bars, s_dep + 4, ndep0);
            fence_async_smem();
            mbar_expect_tx(b_prep, 40960);
#pragma unroll
            for (int q = 0; q < 4; q++) tma_load(stg + q * 10240, &P.xa, (m5 + 3) * 128 + 64 * (q >> 1), tok0 + 80 * (q & 1), b_prep);
          } else if (R > 0) {
            mbar_arrive(b_prep);
          }
          int sig;
#pragma unroll 1
          for (int g = 0; g < 2; g++) {
            mbar_wait(b_stg + 8 * g, ph_stg);
            if (r == 0 || (r == 4 && helper)) {
              const CUtensorMap* om = r == 0 ? &P.ab_st[layer] : (layer ? &P.out : &P.xb);
              const int c0 = (r == 0 ? ft : m5 + 3) * 128 + 64 * g;
              tma_store(om, c0, tok0, stg + g * 20480);
              tma_store(om, c0, tok0 + 80, stg + g * 20480 + 10240);
              sig = r == 0 ? C_AB + layer * 10 + ft : C_XR + (layer * 13 + T) * 2 + m5;
            } else if (r == 1 || r == 5) {
              tma_store(r == 1 ? &P.xa : (layer ? &P.out : &P.xb), m5 * 128 + 64 * g, tok0 + 80 * kap, stg + g * 10240);
              sig = (r == 1 ? C_X1 + (layer * 13 + T) * 2 : C_X2 + T * 2) + g;
              if (g == 0 && R < NRT - 1) {
                bulk_commit_wait_read(); bulk_wait();
                mbar_arrive(bars + 8 * B_PAIR);
                signal(sig);
                asm volatile("mbarrier.arrive.shared::cluster.b64 _, [%0];" ::"r"(mapa(bars + 8 * B_PAIR, rank ^ 1)) : "memory");
              }
            } else {
              tma_store(&P.h, (r == 4 ? fc : (r - 2) * 10 + mem) * 64, tok0 + 80 * g, stg + g * 10240);
              sig = C_H + (layer * 13 + T) * 3 + (r - 2);
            }
          }
          ph_stg ^= 1;
          const bool with_stats = (r == 1 || r == 5) && R < NRT - 1;
          const int ver = r == 1 ? 1 + 2 * layer : 2;
          if (with_stats) {
            mbar_wait(bars + 8 * B_SST, (ver - 1) & 1);
            float2* st = &g_stats[ver][m5 * 2][tok0 + 80 * kap];
            bulk_store(st, sb + OFF_SST, 640);
            bulk_store(st + SEQP, sb + OFF_SST + 640, 640);
          }
          bulk_commit_wait_read();
          bulk_wait();
          if (r == 0) mbar_arrive(bars + 8 * (B_DEP + 15 + layer));
          if (R < NRT - 1) signal(sig);
        }
      }
    } else {
      if (lane == 0) {
        const uint32_t epoch = ld_rlx(&g_epoch);
        *s_epoch = epoch;
        mbar_arrive(bars + 8 * B_EPOCH);
        signal_all(C_PRO);
        uint32_t ndep = 0;
#pragma unroll 1
        for (int R = 1; R < nrt; R++) {
          const int layer = R >= NR, r = R - NR * layer;
          const int nd = round_ndep(R);
#pragma unroll 1
          for (int d = 0; d < nd; d++) {
            ndep++;
            if (r == 0) wait_cnt(C_X2 + T * 2 + d, 10, epoch, s_dep + 4, ndep);
            else if (r == 1) wait_cnt(C_AB + layer * 10 + ft, 13, epoch, s_dep + 4, ndep);
            else if (r == 2) wait_cnt(C_X1 + (layer * 13 + T) * 2 + d, 10, epoch, s_dep + 4, ndep);
            else wait_cnt(C_H + (layer * 13 + T) * 3 + d, d == 2 ? 7 : 10, epoch, s_dep + 4, ndep);
            mbar_arrive(bars + 8 * (B_DEP + ndep));
          }
        }
        wait_cnt(C_PRO + (lid >> 4 & (NREP - 1)), NCTA, epoch, s_dep + 4, 0xffffffffu);
        if (lid == 0) g_epoch = epoch + 1;
      }
    }
  } else if (warp >= 12) {
    const int u = warp - 12;
    if (pb < NWORK) {
      const int tk = pb * 16, t96 = u * 32 + lane;
      mbar_wait(bars + 8 * B_PRO, 0);
#pragma unroll 1
      for (int i = t96; i < 288; i += 96) {
        const int it = min(i, 259), row = it < 160 ? (it & 15) * 10 + (it >> 4) : it;
        uint4 v[8];
#pragma unroll
        for (int c = 0; c < 8; c++) v[c] = lds128(stg + row * 128 + (((c + lane) & 7) << 4));
        const float2 s = slice_stats(v);
        if (it >= 160) asm volatile("st.shared.f32 [%0], %1;" ::"r"(sb + OFF_SST + (it - 160) * 4), "f"(s.x) : "memory");
        else g_stats[0][it >> 4][tk + (it & 15)] = s;
      }
      bar_sync(3, 96);
      if (u == 0) {
        float t = 0.f;
#pragma unroll
        for (int i = 0; i < 10; i++) t += lds32f(sb + OFF_SST + (min(lane, 9) * 10 + i) * 4);
        g_hs[pt][pb - pt * 13][lane] = t * 64.f;
      }
      if (u == 0) {
        __syncwarp();
        if (lane == 0) {
          signal(C_ST + pb / 10);
          asm volatile("red.relaxed.gpu.global.add.u32 [%0], 1;" ::"l"(g_cnt + (C_HS + pt) * CSTRIDE) : "memory");
        }
      }
    }
    if (threadIdx.x == 416) mbar_arrive(bars + 8 * B_PREP);
    mbar_wait(bars + 8 * B_EPOCH, 0);
    const uint32_t epoch = *s_epoch;
#pragma unroll 1
    for (int q = 0; q < (nrt ? 4 : 0); q++) {
      const int is_g3 = q & 1;
      if (q == 1) {
        if (u > 0 && lid < 108) {
          const int which = lid & 1, cg = (lid >> 1) % 27, half = lid / 54;
          const int t64 = (u - 1) * 32 + lane, rr = t64 >> 3, ch = t64 & 7;
          const __nv_bfloat16* W = (which ? P.pwu : P.pwg) + (size_t)(half * 320 + rr) * FF + cg * 64 + ch * 8;
          float a[8];
#pragma unroll
          for (int i = 0; i < 8; i++) a[i] = 0.f;
#pragma unroll 8
          for (int i = 0; i < 40; i++) {
            const uint4 v = __ldg(reinterpret_cast<const uint4*>(W + (size_t)i * 8 * FF));
            a[0] += bf_lo(v.x); a[1] += bf_hi(v.x); a[2] += bf_lo(v.y); a[3] += bf_hi(v.y);
            a[4] += bf_lo(v.z); a[5] += bf_hi(v.z); a[6] += bf_lo(v.w); a[7] += bf_hi(v.w);
          }
#pragma unroll
          for (int i = 0; i < 8; i++) {
            a[i] += __shfl_xor_sync(0xffffffffu, a[i], 8);
            a[i] += __shfl_xor_sync(0xffffffffu, a[i], 16);
          }
          float* sx = reinterpret_cast<float*>(smem_raw + OFF_FEAT + 512);
          if (u == 2 && lane < 8) {
#pragma unroll
            for (int i = 0; i < 8; i++) sx[lane * 8 + i] = a[i];
          }
          bar_sync(4, 64);
          if (u == 1 && lane < 8) {
#pragma unroll
            for (int i = 0; i < 8; i++) g_cs[half][which][cg * 64 + lane * 8 + i] = a[i] + sx[lane * 8 + i];
          }
          __syncwarp();
          if (u == 1 && lane == 0) signal_all(C_PRO2);
        }
        if (lane == 0) wait_cnt(C_PRO2 + (lid >> 4 & (NREP - 1)), 108, epoch, s_dep + 4, 0xffffffffu);
        __syncwarp();
        const int f = u == 2 ? fc : u * 10 + mem;
        const float4 c0 = ld_l2(reinterpret_cast<const float4*>(&g_cs[0][lane >> 4][f * 64]) + (lane & 15));
        const float4 c1 = ld_l2(reinterpret_cast<const float4*>(&g_cs[1][lane >> 4][f * 64]) + (lane & 15));
        sts128(sb + OFF_FEAT + 512 * (u + 1) + lane * 16, __float_as_uint(c0.x + c1.x), __float_as_uint(c0.y + c1.y),
               __float_as_uint(c0.z + c1.z), __float_as_uint(c0.w + c1.w));
      }
      if (q > 0) mbar_wait(bars + 8 * (B_DEP + (q == 1 ? 3 : (q == 2 ? 8 : 11))), 0);
      if (lane == 0 && q == 0) wait_cnt(C_ST + T, 10, epoch, s_dep + 4, 0);
      if (lane == 1 && q == 0 && u == 0) wait_cnt(C_HS + ft, 13, epoch, s_dep + 4, 0);
      __syncwarp();
      const int p = min(u * 27 + lane, 79);
      const float2* st = &g_stats[q][0][tok0];
      float4 v[10];
#pragma unroll
      for (int i = 0; i < 10; i++) v[i] = ld_l2(reinterpret_cast<const float4*>(st + i * SEQP) + p);
      if (q == 0 && u == 0) {
#pragma unroll
        for (int i = 0; i < 4; i++) {
          const int row = lane + 32 * i, tt = min(row / 10, 12);
          const uint32_t hv = ld_rlx(reinterpret_cast<const uint32_t*>(&g_hs[ft][tt][row - min(tt * 10, 118)]));
          asm volatile("st.shared.u32 [%0], %1;" ::"r"(sb + OFF_FEAT + row * 4), "r"(hv) : "memory");
        }
      }
      float ma = 0.f, mb = 0.f, va = 0.f, vb = 0.f, qa = 0.f, qb = 0.f;
#pragma unroll
      for (int i = 0; i < 10; i++) { ma += v[i].x; va += v[i].y; mb += v[i].z; vb += v[i].w; }
      ma *= 0.1f; mb *= 0.1f;
#pragma unroll
      for (int i = 0; i < 10; i++) { const float a = v[i].x - ma, b = v[i].z - mb; qa += a * a; qb += b * b; }
      va = (va + 64.f * qa) * (1.f / 640.f) + 1e-5f; vb = (vb + 64.f * qb) * (1.f / 640.f) + 1e-5f;
      const float sc = is_g3 ? -1.4426950408889634f : 1.f;
      const uint32_t tb = sb + (is_g3 ? OFF_TOKB : OFF_TOKA);
      sts128(tb + p * 16, __float_as_uint(ma), __float_as_uint(rsqrtf(va) * sc), __float_as_uint(mb), __float_as_uint(rsqrtf(vb) * sc));
      if (is_g3) sts64f(tb + 1280 + p * 8, va, vb);
      warp_arrive(bars + 8 * B_LN, lane);
    }
  } else {
    const int wg = warp >> 2, tid = threadIdx.x & 127, w = warp & 3;
    const uint32_t b_prep = bars + 8 * B_PREP, b_stg = bars + 8 * (B_STG + wg);
    uint32_t ph_prep = 0, xph = 0;
    Ring ring{0, 0};
    const int rowA = 16 * w + (lane >> 2);
    const int q2 = (lane & 3) * 2;
    const int trow = (lane & 7) + ((lane >> 4) << 3);
    const uint32_t toff = trow * 128 + (((2 * w + ((lane >> 3) & 1)) ^ (trow & 7)) << 4);
    const uint32_t mystg = stg + wg * 10240;

#pragma unroll 1
    for (int R = 0; R < nrt; R++) {
      const int layer = R >= NR, r = R - NR * layer;
      if (r == 4 && mem == 5) continue;
      if (r == 0) {
        float acc1[1][80];
        mainloop<1, 0>(acc1, sb, ring, 10, wg, lane, ph_prep);
        float (&acc)[80] = acc1[0];
        mbar_wait(bars + 8 * B_LN, 0);
        mbar_wait(b_prep, ph_prep);
        const float hA = lds32f(sb + OFF_FEAT + (wg * 64 + rowA) * 4), hB = lds32f(sb + OFF_FEAT + (wg * 64 + rowA + 8) * 4);
        const uint32_t so = stg + wg * 20480 + toff;
        uint32_t pk[40];
#pragma unroll
        for (int j = 0; j < 20; j++) {
          const float4 s0 = lds128f(sb + OFF_TOKA + (j * 8 + q2) * 8);
          const float* a = &acc[j * 4];
          pk[j * 2] = pack_bf16(s0.y * (a[0] - s0.x * hA), s0.w * (a[1] - s0.z * hA));
          pk[j * 2 + 1] = pack_bf16(s0.y * (a[2] - s0.x * hB), s0.w * (a[3] - s0.z * hB));
        }
#pragma unroll
        for (int jp = 0; jp < 10; jp++) stsm4t(so + jp * 2048, pk[jp * 4], pk[jp * 4 + 1], pk[jp * 4 + 2], pk[jp * 4 + 3]);
      } else if (r == 1 || r == 5 || (r == 4 && helper)) {
        float acc1[1][80];
        mainloop<1, 1>(acc1, sb, ring, r == 1 ? 32 : (r == 4 ? 5 : (kap && m5 < 3 ? 16 : 11)), wg, lane, ph_prep);
        float (&acc)[80] = acc1[0];
        if (r == 4) {
          const uint32_t so = stg + wg * 20480 + toff;
          mbar_wait(b_prep, ph_prep);
#pragma unroll
          for (int hf = 0; hf < 2; hf++) {
            uint32_t rs[5][4];
#pragma unroll
            for (int jp = 0; jp < 5; jp++) ldsm4t(so + (hf * 5 + jp) * 2048, rs[jp][0], rs[jp][1], rs[jp][2], rs[jp][3]);
#pragma unroll
            for (int jp = 0; jp < 5; jp++) {
              const float* a = &acc[hf * 40 + jp * 8];
              stsm4t(so + (hf * 5 + jp) * 2048, pack_bf16(a[0] + bf_lo(rs[jp][0]), a[1] + bf_hi(rs[jp][0])), pack_bf16(a[2] + bf_lo(rs[jp][1]), a[3] + bf_hi(rs[jp][1])),
                     pack_bf16(a[4] + bf_lo(rs[jp][2]), a[5] + bf_hi(rs[jp][2])), pack_bf16(a[6] + bf_lo(rs[jp][3]), a[7] + bf_hi(rs[jp][3])));
            }
          }
          ph_prep ^= 1;
          fence_async_smem();
          warp_arrive(b_stg, lane);
          continue;
        }
        mbar_wait_cluster(bars + 8 * B_XFREE, xph);
        const uint32_t rdst = mapa(mystg + 20480 + tid * 16, rank ^ 1), rbar = mapa(bars + 8 * (B_XFULL + wg), rank ^ 1);
#pragma unroll
        for (int i = 0; i < 5; i++) {
          const float* a = &acc[40 + i * 8];
          asm volatile("st.async.weak.shared::cluster.mbarrier::complete_tx::bytes.v4.b32 [%0], {%1,%2,%3,%4}, [%5];"
                       ::"r"(rdst + i * 2048), "r"(pack_bf16(a[0], a[1])), "r"(pack_bf16(a[2], a[3])), "r"(pack_bf16(a[4], a[5])),
                         "r"(pack_bf16(a[6], a[7])), "r"(rbar) : "memory");
        }
        const float s1 = (r == 1 && kap) ? -1.f : 1.f, s2 = (r == 1 && !kap) ? -1.f : 1.f;
        mbar_wait(b_prep, ph_prep);
        uint32_t rs[5][4];
#pragma unroll
        for (int jp = 0; jp < 5; jp++) ldsm4t(mystg + toff + jp * 2048, rs[jp][0], rs[jp][1], rs[jp][2], rs[jp][3]);
#pragma unroll
        for (int jp = 0; jp < 5; jp++) {
          const uint32_t r0 = rs[jp][0], r1 = rs[jp][1], r2 = rs[jp][2], r3 = rs[jp][3];
          float* a = &acc[jp * 8];
          a[0] = fmaf(s1, a[0], bf_lo(r0)); a[1] = fmaf(s1, a[1], bf_hi(r0)); a[2] = fmaf(s1, a[2], bf_lo(r1)); a[3] = fmaf(s1, a[3], bf_hi(r1));
          a[4] = fmaf(s1, a[4], bf_lo(r2)); a[5] = fmaf(s1, a[5], bf_hi(r2)); a[6] = fmaf(s1, a[6], bf_lo(r3)); a[7] = fmaf(s1, a[7], bf_hi(r3));
        }
        mbar_wait_cluster(bars + 8 * (B_XFULL + wg), xph); xph ^= 1;
        uint4 pv[5];
#pragma unroll
        for (int jp = 0; jp < 5; jp++) pv[jp] = lds128(mystg + 20480 + jp * 2048 + tid * 16);
#pragma unroll
        for (int jp = 0; jp < 5; jp++) {
          const uint4 v = pv[jp];
          const float* a = &acc[jp * 8];
          stsm4t(mystg + toff + jp * 2048, pack_bf16(fmaf(s2, bf_lo(v.x), a[0]), fmaf(s2, bf_hi(v.x), a[1])),
                 pack_bf16(fmaf(s2, bf_lo(v.y), a[2]), fmaf(s2, bf_hi(v.y), a[3])),
                 pack_bf16(fmaf(s2, bf_lo(v.z), a[4]), fmaf(s2, bf_hi(v.z), a[5])),
                 pack_bf16(fmaf(s2, bf_lo(v.w), a[6]), fmaf(s2, bf_hi(v.w), a[7])));
        }
      } else {
        float acc[2][40];
        mainloop<2, 1>(acc, sb, ring, 10, wg, lane, ph_prep);
        mbar_wait(bars + 8 * B_LN, 1);
        float cs[4];
#pragma unroll
        for (int i = 0; i < 4; i++) cs[i] = lds32f(sb + OFF_FEAT + 512 * (r - 1) + ((i >> 1) * 64 + rowA + (i & 1) * 8) * 4);
        const uint32_t tb = sb + OFF_TOKB + (wg * 80 + q2) * 8, vb = sb + OFF_TOKB + 1280 + (wg * 80 + q2) * 4;
        uint32_t hp[20];
#pragma unroll
        for (int j = 0; j < 10; j++) {
          const float4 s = lds128f(tb + j * 64);
          const float2 ve = lds64f(vb + j * 32);
          float hv[4];
#pragma unroll
          for (int e = 0; e < 4; e++) {
            const float mean = (e & 1) ? s.z : s.x, c1 = (e & 1) ? s.w : s.y, v = (e & 1) ? ve.y : ve.x;
            const float g = acc[0][j * 4 + e] - mean * cs[e >> 1];
            const float u = acc[1][j * 4 + e] - mean * cs[2 + (e >> 1)];
            hv[e] = (g * u) * rcp_fast(fmaf(ex2_fast(g * c1), v, v));
          }
          hp[j * 2] = pack_bf16(hv[0], hv[1]);
          hp[j * 2 + 1] = pack_bf16(hv[2], hv[3]);
        }
        mbar_wait(b_prep, ph_prep);
#pragma unroll
        for (int jp = 0; jp < 5; jp++) stsm4t(mystg + toff + jp * 2048, hp[jp * 4], hp[jp * 4 + 1], hp[jp * 4 + 2], hp[jp * 4 + 3]);
      }
      ph_prep ^= 1;
      fence_async_smem();
      warp_arrive(b_stg, lane);
      if ((r == 1 || r == 5) && R < NRT - 1) {
        bar_sync(1 + wg, 128);
        const int t = min(tid, 79);
        uint4 x[8];
#pragma unroll
        for (int c = 0; c < 8; c++) x[c] = lds128(mystg + t * 128 + (((c + t) & 7) << 4));
        const float2 s = slice_stats(x);
        sts64f(sb + OFF_SST + wg * 640 + t * 8, s.x, s.y);
        fence_async_smem();
        warp_arrive(bars + 8 * B_SST, lane);
      }
    }
  }
}

typedef CUresult (*EncodeFn)(CUtensorMap*, CUtensorMapDataType, cuuint32_t, void*, const cuuint64_t*, const cuuint64_t*,
                             const cuuint32_t*, const cuuint32_t*, CUtensorMapInterleave, CUtensorMapSwizzle,
                             CUtensorMapL2promotion, CUtensorMapFloatOOBfill);

void make_map(EncodeFn enc, CUtensorMap* m, const void* p, uint64_t inner, uint64_t outer, uint32_t bi, uint32_t bo, bool swz = true) {
  cuuint64_t dims[2] = {inner, outer};
  cuuint64_t str[1] = {inner * 2};
  cuuint32_t box[2] = {bi, bo};
  cuuint32_t es[2] = {1, 1};
  enc(m, CU_TENSOR_MAP_DATA_TYPE_BFLOAT16, 2, const_cast<void*>(p), dims, str, box, es, CU_TENSOR_MAP_INTERLEAVE_NONE,
      swz ? CU_TENSOR_MAP_SWIZZLE_128B : CU_TENSOR_MAP_SWIZZLE_NONE, CU_TENSOR_MAP_L2_PROMOTION_L2_256B,
      CU_TENSOR_MAP_FLOAT_OOB_FILL_NONE);
}

}

extern "C" void kernel_launch(void* const* d_in, const int* in_sizes, int n_in, void* d_out, int out_size) {
  (void)in_sizes; (void)n_in; (void)out_size;
  static EncodeFn enc = nullptr;
  static void *abT, *xA, *xB, *h;
  if (!enc) {
    void* fn = nullptr;
    cudaDriverEntryPointQueryResult qr;
    cudaGetDriverEntryPoint("cuTensorMapEncodeTiled", &fn, cudaEnableDefault, &qr);
    enc = (EncodeFn)fn;
    cudaFuncSetAttribute(fused_kernel, cudaFuncAttributeMaxDynamicSharedMemorySize, SMEM_BYTES);
    cudaGetSymbolAddress(&abT, g_abT);
    cudaGetSymbolAddress(&xA, g_xA);
    cudaGetSymbolAddress(&xB, g_xB);
    cudaGetSymbolAddress(&h, g_h);
  }
  const __nv_bfloat16* x0 = (const __nv_bfloat16*)d_in[0];
  const __nv_bfloat16* cr = (const __nv_bfloat16*)d_in[1];
  const __nv_bfloat16* ci = (const __nv_bfloat16*)d_in[2];
  const __nv_bfloat16* hr = (const __nv_bfloat16*)d_in[3];
  const __nv_bfloat16* hi = (const __nv_bfloat16*)d_in[4];
  const __nv_bfloat16* wg = (const __nv_bfloat16*)d_in[6];
  const __nv_bfloat16* wu = (const __nv_bfloat16*)d_in[7];
  const __nv_bfloat16* wd = (const __nv_bfloat16*)d_in[8];
  Params P;
  make_map(enc, &P.hr, hr, DM, DM, 64, 128);
  make_map(enc, &P.hi, hi, DM, DM, 64, 128);
  make_map(enc, &P.x0, x0, DM, SEQ, 64, 80);
  make_map(enc, &P.xa, xA, DM, SEQ, 64, 80);
  make_map(enc, &P.xb, xB, DM, SEQ, 64, 80);
  make_map(enc, &P.out, d_out, DM, SEQ, 64, 80);
  for (int l = 0; l < 2; l++) {
    make_map(enc, &P.ab_ld[l], (__nv_bfloat16*)abT + (size_t)l * SEQ * 1280, 1280, SEQ, 64, 64);
    make_map(enc, &P.ab_st[l], (__nv_bfloat16*)abT + (size_t)l * SEQ * 1280, 1280, SEQ, 64, 80);
  }
  make_map(enc, &P.cr, cr, SEQ, SEQ, 64, 80);
  make_map(enc, &P.ci, ci, SEQ, SEQ, 64, 80);
  make_map(enc, &P.wg, wg, FF, DM, 64, 64);
  make_map(enc, &P.wu, wu, FF, DM, 64, 64);
  make_map(enc, &P.wd, wd, DM, FF, 64, 64);
  make_map(enc, &P.h, h, FF, SEQ, 64, 80);
  P.px0 = x0; P.phr = hr; P.phi = hi; P.pwg = wg; P.pwu = wu; P.pwd = wd; P.pcr = cr; P.pci = ci;
  fused_kernel<<<NCTA, NTHREADS, SMEM_BYTES>>>(P);
}
```
